```python
import torch

def _softmax(x, axis=-1):
    return torch.softmax(x, dim=axis)
def _gelu(x):
    return torch.nn.functional.gelu(x, approximate="tanh")
def _silu(x):
    return torch.nn.functional.silu(x)
def _sigmoid(x):
    return torch.sigmoid(x)
def _layernorm(x, axis=-1, eps=1e-5):
    m = x.mean(dim=axis, keepdim=True)
    v = x.var(dim=axis, keepdim=True, unbiased=False)
    return (x - m) / torch.sqrt(v + eps)
def _scatter_add(tgt, idx, src, axis=0):
    return tgt.clone().index_add_(axis, idx, src)
def _segment_sum(src, seg, n):
    out = torch.zeros((n,) + src.shape[1:], dtype=src.dtype)
    return out.index_add_(0, seg, src)
def _pad(x, pw):
    flat = tuple(v for pair in reversed(pw) for v in pair)
    return torch.nn.functional.pad(x, flat)

kernel_name = 'recurrent_scan__ssm_conv_h3__glu_gated_bilinear__prompt'

def setup_inputs():

    _w = (lambda a: (lambda t: t.to(torch.bfloat16) if t.is_floating_point() else t)(torch.as_tensor(a)))
    def _A_setup():
        B, S, D = 1, 2048, 512
        ks = 4
        return {
            "q": _w((lambda *s: torch.randn(*s, dtype=torch.bfloat16) * 0.05)(B, S, D)),
            "k": _w((lambda *s: torch.randn(*s, dtype=torch.bfloat16) * 0.8)(B, S, D)),
            "v": _w((lambda *s: torch.randn(*s, dtype=torch.bfloat16) * 0.8)(B, S, D)),
            "shift_k": _w((lambda *s: torch.randn(*s, dtype=torch.bfloat16) * 0.8)(D, ks) * 0.5),
            "ssm_k": _w((lambda *s: torch.randn(*s, dtype=torch.bfloat16) * 0.8)(D, S) * (1.0 / S ** 0.5)),
            "ssm_D": _w((lambda *s: torch.randn(*s, dtype=torch.bfloat16) * 0.8)(D)),
        }
    _A_in = _A_setup()

    def _B_setup():
        B, S, D, F = 1, 2048, 512, 1376
        return {
            "x": _w((lambda *s: torch.randn(*s, dtype=torch.bfloat16) * 0.05)(B, S, D)),
            "w_gate": _w((lambda *s: torch.randn(*s, dtype=torch.bfloat16) * 0.2)(D, F) * (D ** -0.5)),
            "w_up": _w((lambda *s: torch.randn(*s, dtype=torch.bfloat16) * 0.2)(D, F) * (D ** -0.5)),
            "w_down": _w((lambda *s: torch.randn(*s, dtype=torch.bfloat16) * 0.2)(F, D) * (F ** -0.5)),
        }
    _B_in = _B_setup()

    return {
        "A_q": _A_in["q"],
        "A_k": _A_in["k"],
        "A_v": _A_in["v"],
        "A_shift_k": _A_in["shift_k"],
        "A_ssm_k": _A_in["ssm_k"],
        "A_ssm_D": _A_in["ssm_D"],
        "B_x": _B_in["x"],
        "B_w_gate": _B_in["w_gate"],
        "B_w_up": _B_in["w_up"],
        "B_w_down": _B_in["w_down"],
    }

def reference(A_q, A_k, A_v, A_shift_k, A_ssm_k, A_ssm_D, B_x, B_w_gate, B_w_up, B_w_down):
    def _A_ref(q, k, v, shift_k, ssm_k, ssm_D):
        B, S, D = q.shape
        ks = shift_k.shape[-1]
        k_pad = _pad(k, ((0, 0), (ks - 1, 0), (0, 0)))
        k_shift = torch.zeros_like(k)
        for t in range(ks):
            k_shift = k_shift + k_pad[:, t:t + S, :] * shift_k[:, ks - 1 - t][None, None, :]
        kv = k_shift * v
        L = 2 * S
        kv_pad = _pad(kv, ((0, 0), (0, S), (0, 0)))
        kf_pad = _pad(ssm_k, ((0, 0), (0, S)))
        kv_f = (lambda x, axes=(-2,-1): torch.fft.rfft2(x.float(), dim=axes))(kv_pad[:, None, :, :], axes=(1, 2))
        kf_f = (lambda x, axes=(-2,-1): torch.fft.rfft2(x.float(), dim=axes))(kf_pad[:, None, :], axes=(1, 2))
        kf_f = (lambda x, *d: x.permute(*d))(kf_f, 1, 2, 0)
        y_f = kv_f * kf_f[None, :, :, :]
        y = (lambda x, s, axes=(-2,-1): torch.fft.irfft2(x, s=s, dim=axes).to(torch.bfloat16))(y_f, (1, L), axes=(1, 2))[:, 0, :S, :]
        y = y + kv * ssm_D[None, None, :]
        return q * y

    def _B_ref(x, w_gate, w_up, w_down):
        g = torch.einsum("bsd,df->bsf", x, w_gate)
        u = torch.einsum("bsd,df->bsf", x, w_up)
        h = g * u
        return torch.einsum("bsf,fd->bsd", h, w_down)

    x = A_q
    xn = _layernorm(x, axis=-1)
    s = _A_ref(xn, A_k, A_v, A_shift_k, A_ssm_k, A_ssm_D)
    g = _silu(_B_ref(xn, B_w_gate, B_w_up, B_w_down))
    return x + s * g
```

```cpp
#include <cuda_runtime.h>
#include <cuda.h>
#include <cuda_bf16.h>
#include <stdint.h>

namespace {

constexpr int S_ = 2048, D_ = 512, F_ = 1376;
constexpr int HP = 1408;
constexpr int URP = 2048;
constexpr int FT = 176;

__device__ __align__(1024) __nv_bfloat16 g_h[S_ * HP];
__device__ __align__(1024) __nv_bfloat16 g_ur[D_ * URP];
__device__ __align__(1024) __nv_bfloat16 g_yT[D_ * S_];
__device__ __align__(1024) float2 g_stats[S_];
__device__ __align__(1024) float g_cs[4 * 2 * F_];
__device__ __align__(128) unsigned g_cnt[32];
__device__ __align__(128) unsigned g_hcnt[16 * 2 * 8];
constexpr int CNT_KV = 0, CNT_DONE = 1, CNT_Y = 10  , CNT_AUX = 18;
#define TICK(i) do {} while (0)
#define TICKP(c, i) do {} while (0)

constexpr uint32_t ST1 = 32768;
constexpr int NST1 = 5;
constexpr uint32_t ST1_BYTES = 8192 + 2 * (4096 + 4096 + 3072);
constexpr uint32_t SL2 = 24576;
constexpr uint32_t UR_B = 4480, UR_TX = URP * 2;
static_assert(UR_B + 2 * 4608 <= 14336, "conv buffer");
constexpr uint32_t OFF_SCR0 = 0;
constexpr uint32_t OFF_R2 = 34816;
constexpr int NSL2 = 6;
constexpr uint32_t OFF_STG = OFF_R2 + 2 * SL2;
constexpr uint32_t OFF_SCR1 = OFF_STG;
constexpr uint32_t OFF_C2 = OFF_R2 + NSL2 * SL2;
constexpr uint32_t OFF_X = 196608;
constexpr uint32_t OFF_C0 = OFF_X, OFF_C1 = OFF_X + 14336, OFF_C3 = OFF_C0;
constexpr uint32_t OFF_BAR = OFF_X + 28672;
constexpr uint32_t OFF_CS = OFF_BAR + 640;
constexpr uint32_t OFF_ST1 = OFF_CS + 1408;
constexpr uint32_t OFF_ST2 = OFF_ST1 + 1024;
constexpr uint32_t OFF_PUB = OFF_ST2 + 1024;
constexpr uint32_t SMEM_BYTES = OFF_PUB + 512 + 1024;
constexpr uint32_t OFF_WT = NST1 * ST1, WT_BYTES = 128 * 88 * 2;
constexpr uint32_t OFF_KT = OFF_WT + WT_BYTES, KT_BYTES = 131 * 128;
constexpr uint32_t OFF_VT = OFF_KT + KT_BYTES, VT_BYTES = 128 * 128;
constexpr uint32_t OFF_KVS = OFF_WT;
constexpr uint32_t OFF_CSL = OFF_WT + 16384;
constexpr uint32_t OFF_FX = 0, OFF_FY = 16384, OFF_FF = OFF_C1, OFF_FS = OFF_C2, OFF_FO = OFF_STG;
constexpr int B_FULL1 = 0, B_FULL2 = 5, B_KFULL = 11, B_KVST = 15, B_AUXIN = 16, B_WTIN = 17, B_XFULL = 18, B_YFULL = 19,
              B_CONVFREE = 20, B_GATH = 21, B_CSRDY = 22, B_EMPTY1 = 23, B_HST = 28, B_YST = 30, B_HFREE = 34, B_HST2 = 35,
              B_CFULL = 39, B_EMPTY2 = 43, B_AUXFREE = 49, B_S3FREE = 50, B_STD = 51  , B_COUNT = 52;

struct Params {
  CUtensorMap m_x, m_wg64, m_wg48, m_wu64, m_wu48, m_h64, m_h48, m_wd, m_yT, m_out, m_k, m_v, m_ur, m_xt, m_wgp, m_wup;
  const __nv_bfloat16 *x, *k, *v, *shift_k, *ssm_k, *ssm_D, *wg, *wu, *wd;
};

__device__ __forceinline__ uint32_t smem_u32(const void* p) { return (uint32_t)__cvta_generic_to_shared(p); }
__device__ __forceinline__ void mbar_init(uint32_t bar, uint32_t cnt) {
  asm volatile("mbarrier.init.shared::cta.b64 [%0], %1;" ::"r"(bar), "r"(cnt) : "memory");
}
__device__ __forceinline__ void mbar_expect_tx(uint32_t bar, uint32_t bytes) {
  asm volatile("mbarrier.arrive.expect_tx.shared::cta.b64 _, [%0], %1;" ::"r"(bar), "r"(bytes) : "memory");
}
__device__ __forceinline__ void mbar_arrive(uint32_t bar) {
  asm volatile("mbarrier.arrive.shared::cta.b64 _, [%0];" ::"r"(bar) : "memory");
}
__device__ __forceinline__ void mbar_arrive_both(uint32_t bar, uint32_t peer) {
  asm volatile("mbarrier.arrive.shared::cta.b64 _, [%0];" ::"r"(bar) : "memory");
  asm volatile(
      "{ .reg .b32 ra; mapa.shared::cluster.u32 ra, %0, %1; mbarrier.arrive.shared::cluster.b64 _, [ra]; }" ::"r"(bar),
      "r"(peer)
      : "memory");
}
__device__ __forceinline__ bool mbar_try(uint32_t bar, uint32_t parity) {
  uint32_t ok;
  asm volatile(
      "{ .reg .pred p; mbarrier.try_wait.parity.shared::cta.b64 p, [%1], %2; selp.u32 %0,1,0,p; }"
      : "=r"(ok)
      : "r"(bar), "r"(parity)
      : "memory");
  return ok;
}
__device__ __forceinline__ void mbar_wait(uint32_t bar, uint32_t parity) {
  asm volatile(
      "{\n"
      ".reg .pred p, q;\n"
      ".reg .u32 it;\n"
      "mov.u32 it, 0;\n"
      "WAIT_LOOP:\n"
      "mbarrier.try_wait.parity.shared::cta.b64 p, [%0], %1, 0x4000;\n"
      "@p bra WAIT_DONE;\n"
      "add.u32 it, it, 1;\n"
      "setp.lt.u32 q, it, 262144;\n"
      "@q bra WAIT_LOOP;\n"
      "trap;\n"
      "WAIT_DONE:\n"
      "}\n" ::"r"(bar),
      "r"(parity)
      : "memory");
}
__device__ __forceinline__ void mbar_wait_slow(uint32_t bar, uint32_t parity, int lane) {
  (void)lane;
  asm volatile(
      "{\n"
      ".reg .pred p, q;\n"
      ".reg .u32 it;\n"
      "mov.u32 it, 0;\n"
      "SWAIT_LOOP:\n"
      "mbarrier.try_wait.parity.shared::cta.b64 p, [%0], %1, 0x4000;\n"
      "@p bra SWAIT_DONE;\n"
      "add.u32 it, it, 1;\n"
      "setp.lt.u32 q, it, 262144;\n"
      "@q bra SWAIT_LOOP;\n"
      "trap;\n"
      "SWAIT_DONE:\n"
      "}\n" ::"r"(bar),
      "r"(parity)
      : "memory");
}
__device__ __forceinline__ void mbar_arrive_warp(uint32_t bar, int lane) {
  __syncwarp();
  if (lane == 0) mbar_arrive(bar);
}
__device__ __forceinline__ void tma_load(uint32_t dst, const CUtensorMap* m, uint32_t bar, int c0, int c1) {
  asm volatile(
      "cp.async.bulk.tensor.2d.shared::cluster.global.mbarrier::complete_tx::bytes [%0], [%1, {%3,%4}], [%2];" ::"r"(dst),
      "l"(m), "r"(bar), "r"(c0), "r"(c1)
      : "memory");
}
__device__ __forceinline__ void tma_load_mc(uint32_t dst, const CUtensorMap* m, uint32_t bar, int c0, int c1) {
  asm volatile(
      "cp.async.bulk.tensor.2d.shared::cluster.global.mbarrier::complete_tx::bytes.multicast::cluster [%0], [%1, "
      "{%3,%4}], [%2], %5;" ::"r"(dst),
      "l"(m), "r"(bar), "r"(c0), "r"(c1), "h"((uint16_t)3)
      : "memory");
}
__device__ __forceinline__ void tma_store(const CUtensorMap* m, uint32_t src, int c0, int c1) {
  asm volatile("cp.async.bulk.tensor.2d.global.shared::cta.bulk_group [%0, {%2,%3}], [%1];" ::"l"(m), "r"(src), "r"(c0),
               "r"(c1)
               : "memory");
}
__device__ __forceinline__ void bulk_load(uint32_t dst, const void* src, uint32_t bytes, uint32_t bar) {
  asm volatile("cp.async.bulk.shared::cluster.global.mbarrier::complete_tx::bytes [%0], [%1], %2, [%3];" ::"r"(dst),
               "l"(src), "r"(bytes), "r"(bar)
               : "memory");
}
__device__ __forceinline__ void bulk_prefetch_l2(const void* src, uint32_t bytes) {
  asm volatile("cp.async.bulk.prefetch.L2.global [%0], %1;" ::"l"(src), "r"(bytes) : "memory");
}
__device__ __forceinline__ void bulk_commit() { asm volatile("cp.async.bulk.commit_group;" ::: "memory"); }
__device__ __forceinline__ void bulk_wait_read() { asm volatile("cp.async.bulk.wait_group.read 0;" ::: "memory"); }
__device__ __forceinline__ void bulk_wait_all() { asm volatile("cp.async.bulk.wait_group 0;" ::: "memory"); }
__device__ __forceinline__ void fence_async_smem() { asm volatile("fence.proxy.async.shared::cta;" ::: "memory"); }
__device__ __forceinline__ void named_bar(int id, int n) { asm volatile("bar.sync %0, %1;" ::"r"(id), "r"(n) : "memory"); }
__device__ __forceinline__ void wg_fence() { asm volatile("wgmma.fence.sync.aligned;" ::: "memory"); }
__device__ __forceinline__ void wg_commit() { asm volatile("wgmma.commit_group.sync.aligned;" ::: "memory"); }
template <int N>
__device__ __forceinline__ void wg_wait() {
  asm volatile("wgmma.wait_group.sync.aligned %0;" ::"n"(N) : "memory");
}
__device__ __forceinline__ uint64_t make_desc(uint32_t addr, uint32_t lbo, uint32_t sbo, uint32_t swz) {
  return (uint64_t)((addr & 0x3FFFF) >> 4) | ((uint64_t)(lbo >> 4) << 16) | ((uint64_t)(sbo >> 4) << 32) |
         ((uint64_t)swz << 62);
}
__device__ __forceinline__ void red_flag(unsigned* p, unsigned v) {
  asm volatile("red.relaxed.gpu.global.add.u32 [%0], %1;" ::"l"(p), "r"(v) : "memory");
}
__device__ __forceinline__ void bulk_store(void* dst, uint32_t src, uint32_t bytes) {
  asm volatile("cp.async.bulk.global.shared::cta.bulk_group [%0], [%1], %2;" ::"l"(dst), "r"(src), "r"(bytes) : "memory");
}
__device__ __forceinline__ void sts128(uint32_t a, uint32_t x, uint32_t y, uint32_t z, uint32_t w) {
  asm volatile("st.shared.v4.u32 [%0], {%1,%2,%3,%4};" ::"r"(a), "r"(x), "r"(y), "r"(z), "r"(w) : "memory");
}
__device__ __forceinline__ unsigned ld_acquire(const unsigned* p) {
  unsigned v;
  asm volatile("ld.acquire.gpu.global.u32 %0, [%1];" : "=r"(v) : "l"(p) : "memory");
  return v;
}
__device__ __forceinline__ void wait_counter(const unsigned* p, unsigned target) {
  int it = 0;
  while ((int)(ld_acquire(p) - target) < 0) {
    if (++it > (1 << 22)) __trap();
  }
}
__device__ __forceinline__ uint32_t lds32(uint32_t a) {
  uint32_t v;
  asm volatile("ld.shared.u32 %0, [%1];" : "=r"(v) : "r"(a));
  return v;
}
__device__ __forceinline__ float2 lds64f(uint32_t a) {
  float2 v;
  asm volatile("ld.shared.v2.f32 {%0,%1}, [%2];" : "=f"(v.x), "=f"(v.y) : "r"(a));
  return v;
}
__device__ __forceinline__ float2 lds64f_nv(uint32_t a) {
  float2 v;
  asm("ld.shared.v2.f32 {%0,%1}, [%2];" : "=f"(v.x), "=f"(v.y) : "r"(a));
  return v;
}
__device__ __forceinline__ uint32_t pin_addr(uint32_t a) {
  uint32_t r;
  asm volatile("mov.u32 %0, %1;" : "=r"(r) : "r"(a) : "memory");
  return r;
}
__device__ __forceinline__ uint4 lds128(uint32_t a) {
  uint4 v;
  asm volatile("ld.shared.v4.u32 {%0,%1,%2,%3}, [%4];" : "=r"(v.x), "=r"(v.y), "=r"(v.z), "=r"(v.w) : "r"(a));
  return v;
}
__device__ __forceinline__ void sts64f(uint32_t a, float x, float y) {
  asm volatile("st.shared.v2.f32 [%0], {%1,%2};" ::"r"(a), "f"(x), "f"(y) : "memory");
}
__device__ __forceinline__ void stsm_x4(uint32_t a, uint32_t r0, uint32_t r1, uint32_t r2, uint32_t r3) {
  asm volatile("stmatrix.sync.aligned.m8n8.x4.shared.b16 [%0], {%1,%2,%3,%4};" ::"r"(a), "r"(r0), "r"(r1), "r"(r2),
               "r"(r3)
               : "memory");
}
__device__ __forceinline__ void stsm_x4_t(uint32_t a, uint32_t r0, uint32_t r1, uint32_t r2, uint32_t r3) {
  asm volatile("stmatrix.sync.aligned.m8n8.x4.trans.shared.b16 [%0], {%1,%2,%3,%4};" ::"r"(a), "r"(r0), "r"(r1), "r"(r2),
               "r"(r3)
               : "memory");
}
__device__ __forceinline__ void ldsm_x4(uint32_t a, uint32_t& r0, uint32_t& r1, uint32_t& r2, uint32_t& r3) {
  asm volatile("ldmatrix.sync.aligned.m8n8.x4.shared.b16 {%0,%1,%2,%3}, [%4];"
               : "=r"(r0), "=r"(r1), "=r"(r2), "=r"(r3)
               : "r"(a));
}
__device__ __forceinline__ void ldsm_x4_t(uint32_t a, uint32_t& r0, uint32_t& r1, uint32_t& r2, uint32_t& r3) {
  asm volatile("ldmatrix.sync.aligned.m8n8.x4.trans.shared.b16 {%0,%1,%2,%3}, [%4];"
               : "=r"(r0), "=r"(r1), "=r"(r2), "=r"(r3)
               : "r"(a));
}
__device__ __forceinline__ uint32_t pack_bf16(float lo, float hi) {
  uint32_t r;
  asm("cvt.rn.bf16x2.f32 %0, %1, %2;" : "=r"(r) : "f"(hi), "f"(lo));
  return r;
}
__device__ __forceinline__ float bf_lo(uint32_t v) { return __uint_as_float(v << 16); }
__device__ __forceinline__ float bf_hi(uint32_t v) { return __uint_as_float(v & 0xffff0000u); }
__device__ __forceinline__ float bf_round(float x) { return __bfloat162float(__float2bfloat16_rn(x)); }
__device__ __forceinline__ uint32_t hmul2(uint32_t a, uint32_t b) {
  uint32_t r;
  asm("mul.rn.bf16x2 %0, %1, %2;" : "=r"(r) : "r"(a), "r"(b));
  return r;
}
__device__ __forceinline__ uint32_t hadd2(uint32_t a, uint32_t b) {
  uint32_t r;
  asm("add.rn.bf16x2 %0, %1, %2;" : "=r"(r) : "r"(a), "r"(b));
  return r;
}
__device__ __forceinline__ uint32_t hsub2(uint32_t a, uint32_t b) {
  uint32_t r;
  asm("sub.rn.bf16x2 %0, %1, %2;" : "=r"(r) : "r"(a), "r"(b));
  return r;
}

template<int N> __device__ __forceinline__ void wgmma_rs(float* d, uint32_t a0, uint32_t a1, uint32_t a2, uint32_t a3, uint64_t descB, int scaleD);
template<int N,int TA,int TB> __device__ __forceinline__ void wgmma_ss(float* d, uint64_t descA, uint64_t descB, int scaleD);
template<> __device__ __forceinline__ void wgmma_rs<32>(float* d, uint32_t a0, uint32_t a1, uint32_t a2, uint32_t a3, uint64_t descB, int scaleD){
  asm volatile("{\n.reg .pred p;\nsetp.ne.b32 p, %21, 0;\n"
    "wgmma.mma_async.sync.aligned.m64n32k16.f32.bf16.bf16 {%0,%1,%2,%3,%4,%5,%6,%7,%8,%9,%10,%11,%12,%13,%14,%15}, {%16,%17,%18,%19}, %20, p, 1, 1, 0;\n}\n"
    : "+f"(d[0]),"+f"(d[1]),"+f"(d[2]),"+f"(d[3]),"+f"(d[4]),"+f"(d[5]),"+f"(d[6]),"+f"(d[7]),"+f"(d[8]),"+f"(d[9]),"+f"(d[10]),"+f"(d[11]),"+f"(d[12]),"+f"(d[13]),"+f"(d[14]),"+f"(d[15])
    : "r"(a0), "r"(a1), "r"(a2), "r"(a3), "l"(descB), "r"(scaleD));
}
__device__ __forceinline__ void wgmma_rs_init32(float* d, uint32_t a0, uint32_t a1, uint32_t a2, uint32_t a3, uint64_t descB){
  asm volatile("{\n.reg .pred p;\nsetp.ne.b32 p, 0, 0;\n"
    "wgmma.mma_async.sync.aligned.m64n32k16.f32.bf16.bf16 {%0,%1,%2,%3,%4,%5,%6,%7,%8,%9,%10,%11,%12,%13,%14,%15}, {%16,%17,%18,%19}, %20, p, 1, 1, 0;\n}\n"
    : "=f"(d[0]),"=f"(d[1]),"=f"(d[2]),"=f"(d[3]),"=f"(d[4]),"=f"(d[5]),"=f"(d[6]),"=f"(d[7]),"=f"(d[8]),"=f"(d[9]),"=f"(d[10]),"=f"(d[11]),"=f"(d[12]),"=f"(d[13]),"=f"(d[14]),"=f"(d[15])
    : "r"(a0), "r"(a1), "r"(a2), "r"(a3), "l"(descB));
}
template<> __device__ __forceinline__ void wgmma_ss<176,0,1>(float* d, uint64_t descA, uint64_t descB, int scaleD){
  asm volatile("{\n.reg .pred p;\nsetp.ne.b32 p, %90, 0;\n"
    "wgmma.mma_async.sync.aligned.m64n176k16.f32.bf16.bf16 {%0,%1,%2,%3,%4,%5,%6,%7,%8,%9,%10,%11,%12,%13,%14,%15,%16,%17,%18,%19,%20,%21,%22,%23,%24,%25,%26,%27,%28,%29,%30,%31,%32,%33,%34,%35,%36,%37,%38,%39,%40,%41,%42,%43,%44,%45,%46,%47,%48,%49,%50,%51,%52,%53,%54,%55,%56,%57,%58,%59,%60,%61,%62,%63,%64,%65,%66,%67,%68,%69,%70,%71,%72,%73,%74,%75,%76,%77,%78,%79,%80,%81,%82,%83,%84,%85,%86,%87}, %88, %89, p, 1, 1, 0, 1;\n}\n"
    : "+f"(d[0]),"+f"(d[1]),"+f"(d[2]),"+f"(d[3]),"+f"(d[4]),"+f"(d[5]),"+f"(d[6]),"+f"(d[7]),"+f"(d[8]),"+f"(d[9]),"+f"(d[10]),"+f"(d[11]),"+f"(d[12]),"+f"(d[13]),"+f"(d[14]),"+f"(d[15]),"+f"(d[16]),"+f"(d[17]),"+f"(d[18]),"+f"(d[19]),"+f"(d[20]),"+f"(d[21]),"+f"(d[22]),"+f"(d[23]),"+f"(d[24]),"+f"(d[25]),"+f"(d[26]),"+f"(d[27]),"+f"(d[28]),"+f"(d[29]),"+f"(d[30]),"+f"(d[31]),"+f"(d[32]),"+f"(d[33]),"+f"(d[34]),"+f"(d[35]),"+f"(d[36]),"+f"(d[37]),"+f"(d[38]),"+f"(d[39]),"+f"(d[40]),"+f"(d[41]),"+f"(d[42]),"+f"(d[43]),"+f"(d[44]),"+f"(d[45]),"+f"(d[46]),"+f"(d[47]),"+f"(d[48]),"+f"(d[49]),"+f"(d[50]),"+f"(d[51]),"+f"(d[52]),"+f"(d[53]),"+f"(d[54]),"+f"(d[55]),"+f"(d[56]),"+f"(d[57]),"+f"(d[58]),"+f"(d[59]),"+f"(d[60]),"+f"(d[61]),"+f"(d[62]),"+f"(d[63]),"+f"(d[64]),"+f"(d[65]),"+f"(d[66]),"+f"(d[67]),"+f"(d[68]),"+f"(d[69]),"+f"(d[70]),"+f"(d[71]),"+f"(d[72]),"+f"(d[73]),"+f"(d[74]),"+f"(d[75]),"+f"(d[76]),"+f"(d[77]),"+f"(d[78]),"+f"(d[79]),"+f"(d[80]),"+f"(d[81]),"+f"(d[82]),"+f"(d[83]),"+f"(d[84]),"+f"(d[85]),"+f"(d[86]),"+f"(d[87])
    : "l"(descA), "l"(descB), "r"(scaleD));
}
template<> __device__ __forceinline__ void wgmma_ss<128,1,0>(float* d, uint64_t descA, uint64_t descB, int scaleD){
  asm volatile("{\n.reg .pred p;\nsetp.ne.b32 p, %66, 0;\n"
    "wgmma.mma_async.sync.aligned.m64n128k16.f32.bf16.bf16 {%0,%1,%2,%3,%4,%5,%6,%7,%8,%9,%10,%11,%12,%13,%14,%15,%16,%17,%18,%19,%20,%21,%22,%23,%24,%25,%26,%27,%28,%29,%30,%31,%32,%33,%34,%35,%36,%37,%38,%39,%40,%41,%42,%43,%44,%45,%46,%47,%48,%49,%50,%51,%52,%53,%54,%55,%56,%57,%58,%59,%60,%61,%62,%63}, %64, %65, p, 1, 1, 1, 0;\n}\n"
    : "+f"(d[0]),"+f"(d[1]),"+f"(d[2]),"+f"(d[3]),"+f"(d[4]),"+f"(d[5]),"+f"(d[6]),"+f"(d[7]),"+f"(d[8]),"+f"(d[9]),"+f"(d[10]),"+f"(d[11]),"+f"(d[12]),"+f"(d[13]),"+f"(d[14]),"+f"(d[15]),"+f"(d[16]),"+f"(d[17]),"+f"(d[18]),"+f"(d[19]),"+f"(d[20]),"+f"(d[21]),"+f"(d[22]),"+f"(d[23]),"+f"(d[24]),"+f"(d[25]),"+f"(d[26]),"+f"(d[27]),"+f"(d[28]),"+f"(d[29]),"+f"(d[30]),"+f"(d[31]),"+f"(d[32]),"+f"(d[33]),"+f"(d[34]),"+f"(d[35]),"+f"(d[36]),"+f"(d[37]),"+f"(d[38]),"+f"(d[39]),"+f"(d[40]),"+f"(d[41]),"+f"(d[42]),"+f"(d[43]),"+f"(d[44]),"+f"(d[45]),"+f"(d[46]),"+f"(d[47]),"+f"(d[48]),"+f"(d[49]),"+f"(d[50]),"+f"(d[51]),"+f"(d[52]),"+f"(d[53]),"+f"(d[54]),"+f"(d[55]),"+f"(d[56]),"+f"(d[57]),"+f"(d[58]),"+f"(d[59]),"+f"(d[60]),"+f"(d[61]),"+f"(d[62]),"+f"(d[63])
    : "l"(descA), "l"(descB), "r"(scaleD));
}

template <int I, int E>
__device__ __forceinline__ void conv_steps(float (&d)[8][16], const uint32_t* a, uint64_t desc) {
#pragma unroll
  for (int i = I; i < E; i++) {
    const uint32_t* ai = a + 4 * (i - I);
#pragma unroll
    for (int b = 0; b < 8 - (i >> 1); b++) {
      if (i == 0) wgmma_rs_init32(d[b], ai[0], ai[1], ai[2], ai[3], desc + (uint64_t)(32 * b));
      else wgmma_rs<32>(d[b], ai[0], ai[1], ai[2], ai[3], desc + (uint64_t)(16 * i + 32 * b), 1);
    }
  }
}

__device__ __forceinline__ void kv_subtile(uint32_t kt, uint32_t vt, uint32_t w0, uint32_t w1, uint32_t w2, uint32_t w3,
                                           uint32_t stg, int lane, int sub) {
  uint32_t kk[19], vv[16];
#pragma unroll
  for (int i = 0; i < 19; i++) kk[i] = lds32(kt + i * 128);
#pragma unroll
  for (int i = 0; i < 16; i++) vv[i] = lds32(vt + i * 128);
#pragma unroll
  for (int i = 0; i < 16; i++) {
    uint32_t a = hmul2(kk[i], w3);
    a = hadd2(a, hmul2(kk[i + 1], w2));
    a = hadd2(a, hmul2(kk[i + 2], w1));
    a = hadd2(a, hmul2(kk[i + 3], w0));
    vv[i] = hmul2(a, vv[i]);
  }
  const int pos = 112 - 16 * sub;
  const uint32_t row0 = stg + (pos >> 6) * 8192 + lane * 256;
  const int ck = (pos & 63) >> 3, x0 = (2 * lane) & 7;
  sts128(row0 + ((ck ^ x0) << 4), __byte_perm(vv[15], vv[14], 0x5410), __byte_perm(vv[13], vv[12], 0x5410),
         __byte_perm(vv[11], vv[10], 0x5410), __byte_perm(vv[9], vv[8], 0x5410));
  sts128(row0 + (((ck + 1) ^ x0) << 4), __byte_perm(vv[7], vv[6], 0x5410), __byte_perm(vv[5], vv[4], 0x5410),
         __byte_perm(vv[3], vv[2], 0x5410), __byte_perm(vv[1], vv[0], 0x5410));
  sts128(row0 + 128 + ((ck ^ (x0 + 1)) << 4), __byte_perm(vv[15], vv[14], 0x7632), __byte_perm(vv[13], vv[12], 0x7632),
         __byte_perm(vv[11], vv[10], 0x7632), __byte_perm(vv[9], vv[8], 0x7632));
  sts128(row0 + 128 + (((ck + 1) ^ (x0 + 1)) << 4), __byte_perm(vv[7], vv[6], 0x7632), __byte_perm(vv[5], vv[4], 0x7632),
         __byte_perm(vv[3], vv[2], 0x7632), __byte_perm(vv[1], vv[0], 0x7632));
}

__device__ __forceinline__ uint32_t slot2(int r) {
  return OFF_R2 + ((0x325410u >> (r * 4)) & 7u) * SL2;
}

__global__ void __cluster_dims__(2, 1, 1) __launch_bounds__(384, 1) fused_kernel(const __grid_constant__ Params p) {
  extern __shared__ uint8_t smem_raw[];
  const uint32_t sb = (smem_u32(smem_raw) + 1023u) & ~1023u;
  const uint32_t bar0 = sb + OFF_BAR;
  auto BAR = [&](int i) { return bar0 + 8u * (uint32_t)i; };

  const int tid = threadIdx.x;
  const int cta = blockIdx.x;
  const uint32_t rank = cta & 1, peer = rank ^ 1;
  const int pa = cta >> 4, pj = (cta >> 1) & 7;
  const int i1 = 2 * pa + (int)rank;
  const int f0 = min(FT * pj, F_ - FT);
  const int i2 = 2 * pa + (pj & 1);
  const int n2 = 2 * (pj >> 1) + (int)rank;
  const int wg = __shfl_sync(0xffffffffu, tid >> 7, 0);

  uint4 lx[4];
  if (tid < 256) {
    const uint4* xr = reinterpret_cast<const uint4*>(p.x + (size_t)(cta * 16 + (tid >> 5) * 2) * D_) + (tid & 31);
#pragma unroll
    for (int i = 0; i < 4; i++) lx[i] = __ldg(xr + i * 32);
  }
  auto load_stage_plain = [&](int kb) {
    const uint32_t st = sb + kb * ST1, fb = BAR(B_FULL1 + kb);
    mbar_expect_tx(fb, ST1_BYTES);
    tma_load(st, &p.m_x, fb, kb * 32, i1 * 128);
    tma_load(st + 8192, &p.m_wg64, fb, f0, kb * 32);
    tma_load(st + 20480, &p.m_wu64, fb, f0, kb * 32);
    tma_load(st + 8192 + 4096, &p.m_wg64, fb, f0 + 64, kb * 32);
    tma_load(st + 20480 + 4096, &p.m_wu64, fb, f0 + 64, kb * 32);
    tma_load(st + 8192 + 8192, &p.m_wg48, fb, f0 + 128, kb * 32);
    tma_load(st + 20480 + 8192, &p.m_wu48, fb, f0 + 128, kb * 32);
  };
  if (tid == 256) {
    mbar_init(BAR(B_FULL1), 1);
    mbar_init(BAR(B_FULL1 + 1), 1);
    mbar_init(BAR(B_FULL1 + 2), 1);
    mbar_init(BAR(B_WTIN), 1);
    fence_async_smem();
    load_stage_plain(0);
    asm volatile("fence.mbarrier_init.release.cluster;" ::: "memory");
  } else if ((tid & 31) == 0 && tid > 256) {
    if (tid == 288) {
#pragma unroll
      for (int i = 3; i < 23; i++)
        if (i != B_WTIN) mbar_init(BAR(i), i == B_CONVFREE ? 2 : 1);
    } else if (tid == 320) {
#pragma unroll
      for (int i = 23; i < 39; i++) mbar_init(BAR(i), 4);
    } else {
#pragma unroll
      for (int i = 39; i < B_COUNT; i++) mbar_init(BAR(i), i == B_STD ? 8 : 2);
    }
    asm volatile("fence.mbarrier_init.release.cluster;" ::: "memory");
  }
  __syncthreads();
  asm volatile("barrier.cluster.arrive.relaxed.aligned;" ::: "memory");
  if (tid == 256) {
    load_stage_plain(1);
    load_stage_plain(2);
  }

  if (wg == 2) {
    asm volatile("setmaxnreg.dec.sync.aligned.u32 72;");
    const int warp = __shfl_sync(0xffffffffu, tid >> 5, 0);
    const int lane = tid & 31;
    if (warp == 8) {
      if (lane == 0) {
        const CUtensorMap* mw64 = rank ? &p.m_wu64 : &p.m_wg64;
        const CUtensorMap* mw48 = rank ? &p.m_wu48 : &p.m_wg48;
        const uint32_t woff = 8192u + rank * 12288u;
        auto load_kf = [&](uint32_t base, int c) {
          mbar_expect_tx(BAR(B_KFULL + c), 4096);
          bulk_load(base + UR_B + 16, p.ssm_k + (size_t)(4 * cta + c) * S_, 4096, BAR(B_KFULL + c));
        };
        auto load_ur = [&](uint32_t base, int c) {
          mbar_expect_tx(BAR(B_CFULL + c), UR_TX);
          bulk_load(base, g_ur + (size_t)(4 * cta + c) * URP, UR_TX, BAR(B_CFULL + c));
        };
        unsigned target;
        asm volatile("ld.relaxed.gpu.global.u32 %0, [%1];" : "=r"(target) : "l"(&g_cnt[CNT_DONE]) : "memory");
        auto load_w = [&](int kb) {
          const uint32_t st = sb + (kb % NST1) * ST1, fb = BAR(B_FULL1 + kb % NST1);
          mbar_expect_tx(fb, ST1_BYTES);
          tma_load_mc(st + woff, mw64, fb, f0, kb * 32);
          tma_load_mc(st + woff + 4096, mw64, fb, f0 + 64, kb * 32);
          tma_load_mc(st + woff + 8192, mw48, fb, f0 + 128, kb * 32);
        };
        auto load_a = [&](int kb) {
          tma_load(sb + (kb % NST1) * ST1, &p.m_x, BAR(B_FULL1 + kb % NST1), kb * 32, i1 * 128);
        };
        asm volatile("barrier.cluster.wait.acquire; // producer" ::: "memory");
#pragma unroll 1
        for (int kb = 3; kb < NST1; kb++) {
          load_w(kb);
          load_a(kb);
        }
        TICK(28);
#pragma unroll 1
        for (int kb = NST1; kb < 16; kb++) {
          mbar_wait(BAR(B_EMPTY1 + kb % NST1), ((kb / NST1) - 1) & 1);
          load_w(kb);
          load_a(kb);
          if (kb == 5) {
            mbar_expect_tx(BAR(B_WTIN), WT_BYTES);
            tma_load(sb + OFF_WT, (i1 & 8) ? &p.m_wup : &p.m_wgp, BAR(B_WTIN), f0 + ((i1 >> 2) & 1) * 88, (i1 & 3) * 128);
          }
          if (kb == 7) {
            mbar_expect_tx(BAR(B_AUXIN), KT_BYTES + VT_BYTES);
            tma_load(sb + OFF_KT, &p.m_k, BAR(B_AUXIN), (cta & 7) * 64, (cta >> 3) * 128 - 3);
            tma_load(sb + OFF_VT, &p.m_v, BAR(B_AUXIN), (cta & 7) * 64, (cta >> 3) * 128);
          }
          if (kb == 11) {
            bulk_prefetch_l2(p.ssm_k + (size_t)(4 * cta) * S_, 4 * S_ * 2);
            bulk_prefetch_l2(reinterpret_cast<const uint8_t*>(p.wd) + (size_t)cta * 11008, 11008);
          }
        }
        TICK(1);
        target += 128u;
        mbar_wait(BAR(B_CSRDY), 0);
        mbar_wait(BAR(B_AUXFREE), 0);
        load_kf(sb + OFF_C0, 0);
        load_kf(sb + OFF_C1, 1);
        mbar_wait(BAR(B_KVST), 0);
        load_ur(sb + OFF_C0, 0);
        load_ur(sb + OFF_C1, 1);
        load_kf(sb + OFF_C2, 2);
        load_ur(sb + OFF_C2, 2);
        constexpr int n0 = 0;
        const unsigned* hf = g_hcnt + (i2 * 2 + rank) * 8;
        unsigned ready = 0;
        auto load_wd = [&](int it) {
          const int n = n0 + it - (n0 + it >= 22 ? 22 : 0);
          mbar_expect_tx(BAR(B_FULL2 + it % NSL2), SL2);
          tma_load(sb + slot2(it % NSL2) + 16384, &p.m_wd, BAR(B_FULL2 + it % NSL2), n2 * 64, n * 64);
        };
        auto load_h = [&](int it) {
          const int n = n0 + it - (n0 + it >= 22 ? 22 : 0);
          const unsigned need = (1u << min(7, (64 * n) / FT)) | (1u << min(7, (64 * n + 63) / FT));
          int spin = 0;
          while ((ready & need) != need) {
            unsigned c[8];
            asm volatile("ld.volatile.global.v4.u32 {%0,%1,%2,%3}, [%4];" : "=r"(c[0]), "=r"(c[1]), "=r"(c[2]), "=r"(c[3]) : "l"(hf) : "memory");
            asm volatile("ld.volatile.global.v4.u32 {%0,%1,%2,%3}, [%4];" : "=r"(c[4]), "=r"(c[5]), "=r"(c[6]), "=r"(c[7]) : "l"(hf + 4) : "memory");
#pragma unroll
            for (int e = 0; e < 8; e++) ready |= ((int)(c[e] - target) >= 0 ? 1u : 0u) << e;
            if (++spin > (1 << 22)) asm volatile("trap; // h wait");
          }
          tma_load_mc(sb + slot2(it % NSL2) + rank * 8192, &p.m_h64, BAR(B_FULL2 + it % NSL2), n * 64, i2 * 128 + rank * 64);
        };
        mbar_wait(BAR(B_EMPTY1 + 1), 0);
        load_wd(0);
        mbar_wait(BAR(B_EMPTY1 + 2), 0);
        load_wd(1);
        mbar_wait(BAR(B_EMPTY1 + 4), 0);
        load_wd(2);
        load_wd(3);
        TICK(2);
        load_h(0);
        TICK(3);
        load_h(1);
        load_h(2);
        load_h(3);
#pragma unroll 1
        for (int n = 4; n < 22; n++) {
          if (n == 4) mbar_wait(BAR(B_S3FREE), 0);
          if (n >= NSL2) mbar_wait(BAR(B_EMPTY2 + n % NSL2), ((n / NSL2) - 1) & 1);
          load_wd(n);
          load_h(n);
        }
        TICK(4);
      } else {
        asm volatile("barrier.cluster.wait.acquire; // producer idle lanes" ::: "memory");

      }
    } else {
      const int aw = warp - 9;
      const int at = tid - 288;
      unsigned target;
      asm volatile("ld.relaxed.gpu.global.u32 %0, [%1];" : "=r"(target) : "l"(&g_cnt[CNT_DONE]) : "memory");
      const int kvc = (cta & 7) * 64 + 2 * lane, kvt = (cta >> 3) * 128;
      const uint4 wraw = __ldg(reinterpret_cast<const uint4*>(p.shift_k + (size_t)kvc * 4));
      {
        mbar_wait_slow(BAR(B_WTIN), 0, lane);
        TICKP(at == 0, 30);
        const uint32_t a = sb + OFF_WT + min(at, 87) * 16;
        float cs[8];
#pragma unroll
        for (int e = 0; e < 8; e++) cs[e] = 0.f;
#pragma unroll
        for (int hf = 0; hf < 2; hf++) {
          uint4 w[8];
#pragma unroll
          for (int i = 0; i < 8; i++) w[i] = lds128(a + (hf * 8 + i) * (8 * 176));
#pragma unroll
          for (int i = 0; i < 8; i++) {
            cs[0] += bf_lo(w[i].x); cs[1] += bf_hi(w[i].x); cs[2] += bf_lo(w[i].y); cs[3] += bf_hi(w[i].y);
            cs[4] += bf_lo(w[i].z); cs[5] += bf_hi(w[i].z); cs[6] += bf_lo(w[i].w); cs[7] += bf_hi(w[i].w);
          }
        }
        named_bar(3, 96);
        if (at < 88) {
          sts128(sb + OFF_WT + at * 32, __float_as_uint(cs[0]), __float_as_uint(cs[1]), __float_as_uint(cs[2]), __float_as_uint(cs[3]));
          sts128(sb + OFF_WT + at * 32 + 16, __float_as_uint(cs[4]), __float_as_uint(cs[5]), __float_as_uint(cs[6]), __float_as_uint(cs[7]));
        }
        named_bar(3, 96);
        if (at < 88) {
          float v = 0.f;
#pragma unroll
          for (int rg = 0; rg < 8; rg++) v += __uint_as_float(lds32(sb + OFF_WT + rg * 352 + at * 4));
          asm volatile("st.shared.f32 [%0], %1;" ::"r"(sb + OFF_PUB + 128 + at * 4), "f"(v) : "memory");
        }
      }
      asm volatile("barrier.cluster.wait.acquire; // aux" ::: "memory");
      target += 128u;
      fence_async_smem();
      named_bar(3, 96);
      TICKP(at == 0, 7);
      if (aw == 2) {
        if (lane == 0) {
          mbar_wait(BAR(B_STD), 0);
          bulk_store(g_stats + cta * 16, sb + OFF_PUB, 128);
          bulk_store(g_cs + (size_t)(i1 & 3) * (2 * F_) + (i1 >> 3) * F_ + f0 + ((i1 >> 2) & 1) * 88, sb + OFF_PUB + 128, 352);
          bulk_commit();
          bulk_wait_all();
          red_flag(&g_cnt[CNT_AUX], 1u);
          TICK(9);
          wait_counter(&g_cnt[CNT_AUX], target);
          TICK(29);
          mbar_expect_tx(BAR(B_GATH), 8 * FT * 4 + 2048);
          bulk_load(sb + OFF_ST1, g_stats + i1 * 128, 1024, BAR(B_GATH));
          bulk_load(sb + OFF_ST2, g_stats + i2 * 128, 1024, BAR(B_GATH));
#pragma unroll 1
          for (int i = 0; i < 8; i++)
            bulk_load(sb + OFF_CSL + i * (FT * 4), g_cs + (size_t)(i >> 1) * (2 * F_) + (i & 1) * F_ + f0, FT * 4, BAR(B_GATH));
        }
        __syncwarp();
        mbar_wait_slow(BAR(B_GATH), 0, lane);
#pragma unroll 1
        for (int it = lane; it < 88; it += 32) {
          const uint32_t a = sb + OFF_CSL + it * 16;
          float4 sm = make_float4(0.f, 0.f, 0.f, 0.f);
#pragma unroll
          for (int i = 0; i < 4; i++) {
            const uint4 v = lds128(a + i * (2 * FT * 4));
            sm.x += __uint_as_float(v.x); sm.y += __uint_as_float(v.y);
            sm.z += __uint_as_float(v.z); sm.w += __uint_as_float(v.w);
          }
          sts64f(sb + OFF_CS + it * 16, sm.x, sm.y);
          sts64f(sb + OFF_CS + it * 16 + 8, sm.z, sm.w);
        }
        fence_async_smem();
        mbar_arrive_warp(BAR(B_CSRDY), lane);
        TICKP(lane == 0, 14);
      }
      if (aw < 2) {
        const uint32_t w0 = __byte_perm(wraw.x, wraw.z, 0x5410), w1 = __byte_perm(wraw.x, wraw.z, 0x7632);
        const uint32_t w2 = __byte_perm(wraw.y, wraw.w, 0x5410), w3 = __byte_perm(wraw.y, wraw.w, 0x7632);
        __syncwarp();
        mbar_wait_slow(BAR(B_AUXIN), 0, lane);
        TICKP(at == 32, 12);
#pragma unroll 1
        for (int sub = aw; sub < 8; sub += 2)
          kv_subtile(sb + OFF_KT + sub * 2048 + lane * 4, sb + OFF_VT + sub * 2048 + lane * 4, w0, w1, w2, w3, sb + OFF_KVS, lane, sub);
        fence_async_smem();
        named_bar(4, 64);
        TICKP(at == 32, 13);
        if (at == 32) {
          tma_store(&p.m_ur, sb + OFF_KVS, 1920 - kvt, (cta & 7) * 64);
          tma_store(&p.m_ur, sb + OFF_KVS + 8192, 1920 - kvt + 64, (cta & 7) * 64);
          bulk_commit();
          bulk_wait_all();
          mbar_arrive_both(BAR(B_AUXFREE), peer);
          red_flag(&g_cnt[CNT_KV], 1u);
          TICK(8);
          wait_counter(&g_cnt[CNT_KV], target);
          TICK(15);
          mbar_arrive(BAR(B_KVST));
        }
        __syncwarp();
      }
      if (aw < 2 && lane == 0) {
        const int w = aw;
        const uint32_t stg = sb + OFF_STG + w * SL2;
        const int row = i1 * 128 + w * 64;
        mbar_wait(BAR(B_HST2 + 2 * w), 0);
        tma_store(&p.m_h64, stg, f0, row);
        mbar_wait(BAR(B_HST2 + 2 * w + 1), 0);
        tma_store(&p.m_h64, stg + 8192, f0 + 64, row);
        mbar_wait(BAR(B_HST + w), 0);
        tma_store(&p.m_h48, stg + 16384, f0 + 128, row);
        bulk_commit();
        bulk_wait_read();
        mbar_arrive_both(BAR(B_HFREE), peer);
        bulk_wait_all();
        red_flag(&g_hcnt[(i1 * 2 + w) * 8 + pj], 128u);
        if (w == 0) TICK(10);
#pragma unroll 1
        for (int it = 0; it < (w ? 1 : 3); it++) {
          const int c = w ? 1 : (it ? it + 1 : 0);
          mbar_wait(BAR(B_YST + c), 0);
          if (w) mbar_arrive_both(BAR(B_S3FREE), peer);
          const uint32_t cb = sb + (c == 0 ? OFF_C0 : c == 1 ? OFF_C1 : c == 2 ? OFF_C2 : OFF_C3);
          bulk_store(g_yT + (size_t)(4 * cta + c) * S_, cb + UR_B, 4096);
          bulk_commit();
          if (c == 0) {
            bulk_wait_read();
            mbar_expect_tx(BAR(B_KFULL + 3), 4096);
            bulk_load(sb + OFF_C3 + UR_B + 16, p.ssm_k + (size_t)(4 * cta + 3) * S_, 4096, BAR(B_KFULL + 3));
            mbar_expect_tx(BAR(B_CFULL + 3), UR_TX);
            bulk_load(sb + OFF_C3, g_ur + (size_t)(4 * cta + 3) * URP, UR_TX, BAR(B_CFULL + 3));
          }
          if (c == 3 || c == 1) {
            bulk_wait_read();
            mbar_arrive(BAR(B_CONVFREE));
          }
          bulk_wait_all();
          red_flag(&g_cnt[CNT_Y + pa], 2u);
        }
        if (w == 0) TICK(11);
      }
      if (aw == 2) {
#pragma unroll 1
        for (int c = 0; c < 4; c++) {
          const uint32_t ka = sb + (c == 0 ? OFF_C0 : c == 1 ? OFF_C1 : c == 2 ? OFF_C2 : OFF_C3) + UR_B;
          mbar_wait_slow(BAR(B_KFULL + c), 0, lane);
          if (lane == 0) sts128(ka, 0, 0, 0, 0);
          if (lane < 18) sts128(ka - UR_B + 4096 + lane * 16, 0, 0, 0, 0);
          fence_async_smem();
          __syncwarp();
#pragma unroll 1
          for (int j = lane; j < 257; j += 32) {
            const uint4 a = lds128(ka + 16 * j);
            const uint32_t b = lds32(ka + 16 * j + 16);
            asm volatile("st.shared.v4.u32 [%0], {%1,%2,%3,%4};" ::"r"(ka + 4608 + 64 + 16 * j),
                         "r"(__byte_perm(a.x, a.y, 0x5432)), "r"(__byte_perm(a.y, a.z, 0x5432)),
                         "r"(__byte_perm(a.z, a.w, 0x5432)), "r"(__byte_perm(a.w, b, 0x5432))
                         : "memory");
          }
          __syncwarp();
          if (lane == 0) mbar_arrive(BAR(B_CFULL + c));
        }
        if (lane == 0) {
          mbar_wait_slow(BAR(B_CONVFREE), 0, 0);
          mbar_expect_tx(BAR(B_XFULL), 16384);
          tma_load(sb + OFF_FX, &p.m_xt, BAR(B_XFULL), n2 * 64, i2 * 128);
          tma_load(sb + OFF_FX + 8192, &p.m_xt, BAR(B_XFULL), n2 * 64, i2 * 128 + 64);
          wait_counter(&g_cnt[CNT_Y + n2], target);
          TICK(5);
          mbar_expect_tx(BAR(B_YFULL), 16384);
          tma_load(sb + OFF_FY, &p.m_yT, BAR(B_YFULL), i2 * 128, n2 * 64);
          tma_load(sb + OFF_FY + 8192, &p.m_yT, BAR(B_YFULL), i2 * 128 + 64, n2 * 64);
          atomicAdd(&g_cnt[CNT_DONE], 1u);
        }
      }
    }
    __syncwarp();
    if (warp == 8) asm volatile("barrier.cluster.arrive.relaxed;\n barrier.cluster.wait; // producer exit" ::: "memory");
  } else {
    asm volatile("setmaxnreg.inc.sync.aligned.u32 216;");
    const int wt = tid & 127;
    const int wq = wt >> 5, lane = tid & 31;
    const int g = lane >> 2, t = lane & 3;
    const bool sig = (wt == 0);
    const uint32_t dvals = __ldg(reinterpret_cast<const uint32_t*>(p.ssm_D) + 2 * cta) , dvals2 = __ldg(reinterpret_cast<const uint32_t*>(p.ssm_D) + 2 * cta + 1);

    {
      float sm[2], q[2];
#pragma unroll
      for (int i = 0; i < 2; i++) {
        const uint32_t xw[8] = {lx[2 * i].x, lx[2 * i].y, lx[2 * i].z, lx[2 * i].w, lx[2 * i + 1].x, lx[2 * i + 1].y, lx[2 * i + 1].z, lx[2 * i + 1].w};
        float a = 0.f, b = 0.f;
#pragma unroll
        for (int e = 0; e < 8; e++) { a += bf_lo(xw[e]); b += bf_hi(xw[e]); }
        sm[i] = a + b;
      }
#pragma unroll
      for (int o = 16; o > 0; o >>= 1) {
        sm[0] += __shfl_xor_sync(0xffffffffu, sm[0], o);
        sm[1] += __shfl_xor_sync(0xffffffffu, sm[1], o);
      }
#pragma unroll
      for (int i = 0; i < 2; i++) {
        const uint32_t xw[8] = {lx[2 * i].x, lx[2 * i].y, lx[2 * i].z, lx[2 * i].w, lx[2 * i + 1].x, lx[2 * i + 1].y, lx[2 * i + 1].z, lx[2 * i + 1].w};
        sm[i] *= (1.0f / D_);
        float a = 0.f, b = 0.f;
#pragma unroll
        for (int e = 0; e < 8; e++) {
          const float d0 = bf_lo(xw[e]) - sm[i], d1 = bf_hi(xw[e]) - sm[i];
          a = fmaf(d0, d0, a);
          b = fmaf(d1, d1, b);
        }
        q[i] = a + b;
      }
#pragma unroll
      for (int o = 16; o > 0; o >>= 1) {
        q[0] += __shfl_xor_sync(0xffffffffu, q[0], o);
        q[1] += __shfl_xor_sync(0xffffffffu, q[1], o);
      }
      if (lane < 2) {
        const float vb = bf_round((lane ? q[1] : q[0]) * (1.0f / D_));
        sts64f(sb + OFF_PUB + ((tid >> 5) * 2 + lane) * 8, bf_round(lane ? sm[1] : sm[0]),
               1.0f / bf_round(sqrtf(bf_round(vb + 1e-5f))));
        fence_async_smem();
      }
      mbar_arrive_warp(BAR(B_STD), lane);
      TICKP(tid == 0, 6);
    }
    asm volatile("barrier.cluster.wait.acquire.aligned; // consumer" ::: "memory");

    {
      float acc[176];
#pragma unroll
      for (int i = 0; i < 176; i++) acc[i] = 0.f;
#pragma unroll 1
      for (int kb = 0; kb < 16; kb++) {
        const int s = kb % NST1;
        mbar_wait(BAR(B_FULL1 + s), (kb / NST1) & 1);
        TICKP(kb == 0 && tid == 0, 16);
        const uint32_t st = sb + s * ST1;
        const uint64_t da = make_desc(st + wg * 4096, 16, 512, 2);
        const uint64_t dg = make_desc(st + 8192, 4096, 1024, 1);
        const uint64_t du = make_desc(st + 20480, 4096, 1024, 1);
        wg_fence();
        wgmma_ss<176, 0, 1>(acc, da, dg, 1);
        wgmma_ss<176, 0, 1>(acc + 88, da, du, 1);
        wgmma_ss<176, 0, 1>(acc, da + 2, dg + 128, 1);
        wgmma_ss<176, 0, 1>(acc + 88, da + 2, du + 128, 1);
        wg_commit();
        if (kb > 0) {
          wg_wait<1>();
          if (sig) {
            mbar_arrive_both(BAR(B_EMPTY1 + (kb - 1) % NST1), peer);
          }
        }
      }
      wg_wait<0>();
      if (sig) {
        mbar_arrive_both(BAR(B_EMPTY1 + 15 % NST1), peer);
        if (wg == 0) TICK(17);
      }
      named_bar(10, 256);
      mbar_wait_slow(BAR(B_CSRDY), 0, lane);
      const float m0 = __uint_as_float(lds32(sb + OFF_ST1 + (wg * 64 + wq * 16 + g) * 8));
      const float m1 = __uint_as_float(lds32(sb + OFF_ST1 + (wg * 64 + wq * 16 + g + 8) * 8));
      const uint32_t csa = pin_addr(sb + OFF_CS + t * 8);
      const int srow = wq * 16 + ((lane >> 3) & 1) * 8 + (lane & 7);
      const uint32_t stg = sb + OFF_STG + wg * SL2 + srow * 128;
#pragma unroll
      for (int jp = 0; jp < 11; jp++) {
        uint32_t hr[4];
#pragma unroll
        for (int q = 0; q < 2; q++) {
          const int jg = 2 * jp + q;
          const float2 cg = lds64f_nv(csa + jg * 32);
          const float2 cu = lds64f_nv(csa + FT * 4 + jg * 32);
          hr[2 * q + 0] = pack_bf16(fmaf(-m0, cg.x, acc[4 * jg + 0]) * fmaf(-m0, cu.x, acc[88 + 4 * jg + 0]),
                                    fmaf(-m0, cg.y, acc[4 * jg + 1]) * fmaf(-m0, cu.y, acc[88 + 4 * jg + 1]));
          hr[2 * q + 1] = pack_bf16(fmaf(-m1, cg.x, acc[4 * jg + 2]) * fmaf(-m1, cu.x, acc[88 + 4 * jg + 2]),
                                    fmaf(-m1, cg.y, acc[4 * jg + 3]) * fmaf(-m1, cu.y, acc[88 + 4 * jg + 3]));
        }
        const int cgp = 2 * jp + (lane >> 4);
        const uint32_t addr = stg + (cgp >> 3) * 8192 + (((cgp & 7) ^ (lane & 7)) << 4);
        stsm_x4(addr, hr[0], hr[1], hr[2], hr[3]);
        if (jp == 3 || jp == 7) {
          fence_async_smem();
          mbar_arrive_warp(BAR(B_HST2 + 2 * wg + (jp >> 2)), lane);
        }
      }
      fence_async_smem();
      mbar_arrive_warp(BAR(B_HST + wg), lane);
      TICKP(tid == 0, 18);
    }

    {
      const uint32_t scr = sb + (wg ? OFF_SCR1 : OFF_SCR0);
#pragma unroll 1
      for (int cc = 0; cc < (wg ? 1 : 3); cc++) {
        const int chl = wg ? 1 : (cc ? cc + 1 : 0);
        const uint32_t cb = sb + (chl == 0 ? OFF_C0 : chl == 1 ? OFF_C1 : chl == 2 ? OFF_C2 : OFF_C3);
        const uint32_t abase = (g & 1) ? (cb + UR_B + 2 * (16 * wq + 1 + g + 2 * t)) : (cb + UR_B + 4608 + 2 * (16 * wq + 32 + g + 2 * t));
        const uint64_t desc = make_desc(cb, 16, 128, 0);
        float acc[8][16];
        uint32_t a0[16], a1[16];
        auto load_a = [&](uint32_t* a, int b) {
#pragma unroll
          for (int i = 0; i < 4; i++) {
            a[4 * i + 0] = lds32(abase + (4 * b + i) * 256);
            a[4 * i + 1] = lds32(abase + (4 * b + i) * 256 + 128);
            a[4 * i + 2] = lds32(abase + (4 * b + i) * 256 + 16);
            a[4 * i + 3] = lds32(abase + (4 * b + i) * 256 + 144);
          }
        };
        mbar_wait_slow(BAR(B_CFULL + chl), 0, lane);
        TICKP(tid == 0 && cc < 2, 19 + 2 * cc);
        load_a(a0, 0);
        load_a(a1, 1);
        if (chl == 1) named_bar(6, 256);
        wg_fence();
        conv_steps<0, 4>(acc, a0, desc);
        wg_commit();
        conv_steps<4, 8>(acc, a1, desc);
        wg_commit();
        wg_wait<1>();
        load_a(a0, 2);
        wg_fence();
        conv_steps<8, 12>(acc, a0, desc);
        wg_commit();
        wg_wait<1>();
        load_a(a1, 3);
        wg_fence();
        conv_steps<12, 16>(acc, a1, desc);
        wg_commit();
        if (chl == 0) asm volatile("bar.arrive 6, 256;" ::: "memory");
        wg_wait<0>();
        TICKP(tid == 0 && cc < 2, 20 + 2 * cc);
        if (wg) mbar_wait_slow(BAR(B_HFREE), 0, lane);
        named_bar(1 + wg, 128);
        {
          const uint32_t wbase = scr + wq * 8448 + g * 1056;
          if (t < 3) sts64f(wbase + (258 + 2 * t) * 4, 0.f, 0.f);
          __syncwarp();
          const uint32_t wa = wbase + (2 * t - 2 * wq + 8) * 4;
#pragma unroll
          for (int jn = 0; jn < 32; jn++) {
            float z0 = acc[jn >> 2][4 * (jn & 3)], z1 = acc[jn >> 2][4 * (jn & 3) + 1];
            if (jn < 31) { z0 += acc[(jn + 1) >> 2][4 * ((jn + 1) & 3) + 2]; z1 += acc[(jn + 1) >> 2][4 * ((jn + 1) & 3) + 3]; }
            sts64f(wa + jn * 32, z0, z1);
          }
        }
        named_bar(1 + wg, 128);
        {
          const uint32_t ra = scr + (2 * wt + 8) * 4;
          const uint4 ua = lds128(cb + wt * 32), ub = lds128(cb + wt * 32 + 16);
          const uint32_t uw[8] = {ua.x, ua.y, ua.z, ua.w, ub.x, ub.y, ub.z, ub.w};
          const uint32_t dd = __byte_perm((chl & 2) ? dvals2 : dvals, 0, (chl & 1) ? 0x3232 : 0x1010);
          float y0[8], y1[8];
#pragma unroll
          for (int gg = 0; gg < 8; gg++) {
            float2 v = lds64f(ra + gg * 1056);
#pragma unroll
            for (int w = 1; w < 4; w++) {
              const float2 x = lds64f(ra + w * 8448 + gg * 1056);
              v.x += x.x; v.y += x.y;
            }
            y0[gg] = v.x; y1[gg] = v.y;
          }
          uint32_t o[8];
#pragma unroll
          for (int q = 0; q < 8; q++) {
            const float lo = (q < 4) ? y0[7 - 2 * q] : y1[15 - 2 * q];
            const float hi = (q < 4) ? y0[6 - 2 * q] : y1[14 - 2 * q];
            const uint32_t yt = hadd2(pack_bf16(lo, hi), hmul2(uw[q], dd));
            o[7 - q] = __byte_perm(yt, yt, 0x1032);
          }
          const uint32_t ys = cb + UR_B + (2032 - 16 * wt) * 2;
          sts128(ys, o[0], o[1], o[2], o[3]);
          sts128(ys + 16, o[4], o[5], o[6], o[7]);
        }
        fence_async_smem();
        mbar_arrive_warp(BAR(B_YST + chl), lane);
      }
      TICKP(tid == 0, 23);
    }

    {
      uint32_t fpk[16], xr[16], sv[16];
      const uint32_t hb = (wg ^ 1) * 8192;
      const int mi = lane >> 3, l7 = lane & 7;
      const uint32_t ta = ((mi >> 1) * 8 + l7) * 128 + (((2 * wq + (mi & 1)) ^ l7) << 4);
      if (wg == 1) {
        float acc[64], rs2[32];
#pragma unroll
        for (int i = 0; i < 64; i++) acc[i] = 0.f;
#pragma unroll
        for (int j = 0; j < 16; j++) {
          const uint4 st = lds128(sb + OFF_ST2 + (8 * j + 2 * t) * 8);
          rs2[2 * j] = __uint_as_float(st.y) * __uint_as_float(st.y);
          rs2[2 * j + 1] = __uint_as_float(st.w) * __uint_as_float(st.w);
        }
        int r = 0;
        uint32_t ph = 0;
#pragma unroll 1
        for (int n = 0; n < 22; n++) {
          mbar_wait(BAR(B_FULL2 + r), ph);
          TICKP(n == 0 && wt == 0, 24);
          const uint32_t sl = sb + slot2(r);
          const uint64_t da = make_desc(sl + 16384, 8192, 1024, 1);
          const uint64_t db = make_desc(sl, 16, 1024, 1);
          wg_fence();
          wgmma_ss<128, 1, 0>(acc, da, db, 1);
          wgmma_ss<128, 1, 0>(acc, da + 128, db + 2, 1);
          wgmma_ss<128, 1, 0>(acc, da + 256, db + 4, 1);
          wgmma_ss<128, 1, 0>(acc, da + 384, db + 6, 1);
          wg_commit();
          wg_wait<1>();
          if (sig && n > 0 && n < 23 - NSL2) mbar_arrive_both(BAR(B_EMPTY2 + (r ? r - 1 : NSL2 - 1)), peer);
          if (++r == NSL2) { r = 0; ph ^= 1; }
        }
        wg_wait<0>();
        TICKP(wt == 0, 25);
        mbar_wait_slow(BAR(B_XFULL), 0, lane);
#pragma unroll
        for (int i = 0; i < 16; i++) {
          const int j = i >> 1;
          fpk[i] = pack_bf16(acc[2 * i] * rs2[2 * j], acc[2 * i + 1] * rs2[2 * j + 1]);
          asm volatile("st.shared.u32 [%0], %1;" ::"r"(sb + OFF_FF + i * 512 + wt * 4),
                       "r"(pack_bf16(acc[32 + 2 * i] * rs2[16 + 2 * j], acc[33 + 2 * i] * rs2[17 + 2 * j]))
                       : "memory");
        }
        asm volatile("bar.arrive 7, 256;" ::: "memory");
#pragma unroll
        for (int jp = 0; jp < 4; jp++)
          ldsm_x4_t(sb + OFF_FX + ta + jp * 2048, xr[4 * jp], xr[4 * jp + 1], xr[4 * jp + 2], xr[4 * jp + 3]);
      } else {
        mbar_wait_slow(BAR(B_XFULL), 0, lane);
        uint32_t xn[2][16];
#pragma unroll
        for (int hh = 0; hh < 2; hh++) {
#pragma unroll
          for (int jp = 0; jp < 4; jp++)
            ldsm_x4_t(sb + OFF_FX + hh * 8192 + ta + jp * 2048, xr[4 * jp], xr[4 * jp + 1], xr[4 * jp + 2], xr[4 * jp + 3]);
#pragma unroll
          for (int jj = 0; jj < 8; jj++) {
            const uint4 st = lds128(sb + OFF_ST2 + (hh * 64 + 8 * jj + 2 * t) * 8);
            const uint32_t mm = pack_bf16(__uint_as_float(st.x), __uint_as_float(st.z));
#pragma unroll
            for (int h = 0; h < 2; h++) {
              const uint32_t d = hsub2(xr[2 * jj + h], mm);
              xn[hh][2 * jj + h] = pack_bf16(bf_lo(d) * __uint_as_float(st.y), bf_hi(d) * __uint_as_float(st.w));
            }
          }
        }
        mbar_wait_slow(BAR(B_YFULL), 0, lane);
        TICKP(tid == 0, 26);
#pragma unroll
        for (int hh = 0; hh < 2; hh++) {
          const uint32_t ya = sb + OFF_FY + hh * 8192 + (16 * wq + 8 * (mi & 1) + l7) * 128;
#pragma unroll
          for (int jp = 0; jp < 4; jp++)
            ldsm_x4(ya + (((2 * jp + (mi >> 1)) ^ l7) << 4), sv[4 * jp], sv[4 * jp + 1], sv[4 * jp + 2], sv[4 * jp + 3]);
#pragma unroll
          for (int i = 0; i < 16; i++) sv[i] = hmul2(xn[hh][i], sv[i]);
          if (hh == 0) {
#pragma unroll
            for (int i = 0; i < 16; i++)
              asm volatile("st.shared.u32 [%0], %1;" ::"r"(sb + OFF_FS + i * 512 + wt * 4), "r"(sv[i]) : "memory");
            asm volatile("bar.arrive 8, 256;" ::: "memory");
          }
        }
        named_bar(7, 256);
#pragma unroll
        for (int i = 0; i < 16; i++) fpk[i] = lds32(sb + OFF_FF + i * 512 + wt * 4);
      }
#pragma unroll
      for (int i = 0; i < 16; i++) {
        const float fl = bf_lo(fpk[i]), fh = bf_hi(fpk[i]);
        fpk[i] = pack_bf16(__fdividef(fl, 1.0f + __expf(-fl)), __fdividef(fh, 1.0f + __expf(-fh)));
      }
      if (wg == 1) {
        named_bar(8, 256);
#pragma unroll
        for (int i = 0; i < 16; i++) sv[i] = lds32(sb + OFF_FS + i * 512 + wt * 4);
      }
#pragma unroll
      for (int jp = 0; jp < 4; jp++) {
        uint32_t o[4];
#pragma unroll
        for (int e = 0; e < 4; e++) o[e] = hadd2(xr[4 * jp + e], hmul2(sv[4 * jp + e], fpk[4 * jp + e]));
        stsm_x4_t(sb + OFF_FO + hb + ta + jp * 2048, o[0], o[1], o[2], o[3]);
      }
      fence_async_smem();
      named_bar(1 + wg, 128);
      if (sig) {
        tma_store(&p.m_out, sb + OFF_FO + hb, n2 * 64, i2 * 128 + (wg ^ 1) * 64);
        bulk_commit();
        bulk_wait_read();
        if (wg == 0) TICK(27);
      }
    }
  }
}

typedef CUresult (*PFN_encodeTiled)(CUtensorMap*, CUtensorMapDataType, cuuint32_t, void*, const cuuint64_t*,
                                    const cuuint64_t*, const cuuint32_t*, const cuuint32_t*, CUtensorMapInterleave,
                                    CUtensorMapSwizzle, CUtensorMapL2promotion, CUtensorMapFloatOOBfill);

void make_map(PFN_encodeTiled enc, CUtensorMap* m, const void* base, uint64_t inner, uint64_t outer, uint64_t pitch_elems,
              uint32_t box_inner, uint32_t box_outer, CUtensorMapSwizzle sw) {
  cuuint64_t dims[2] = {inner, outer};
  cuuint64_t strides[1] = {pitch_elems * 2};
  cuuint32_t box[2] = {box_inner, box_outer};
  cuuint32_t es[2] = {1, 1};
  CUresult r_ = enc(m, CU_TENSOR_MAP_DATA_TYPE_BFLOAT16, 2, const_cast<void*>(base), dims, strides, box, es,
      CU_TENSOR_MAP_INTERLEAVE_NONE, sw, CU_TENSOR_MAP_L2_PROMOTION_L2_128B, CU_TENSOR_MAP_FLOAT_OOB_FILL_NONE);
  (void)r_;
}

}

extern "C" void kernel_launch(void* const* d_in, const int* in_sizes, int n_in, void* d_out, int out_size) {
  (void)in_sizes; (void)n_in; (void)out_size;
  static PFN_encodeTiled enc = nullptr;
  static void *ph = nullptr, *pyT = nullptr, *pur = nullptr;
  if (!enc) {
    void* fn = nullptr;
    cudaDriverEntryPointQueryResult st;
    cudaGetDriverEntryPoint("cuTensorMapEncodeTiled", &fn, cudaEnableDefault, &st);
    enc = (PFN_encodeTiled)fn;
    cudaGetSymbolAddress(&ph, g_h);
    cudaGetSymbolAddress(&pyT, g_yT);
    cudaGetSymbolAddress(&pur, g_ur);
    cudaFuncSetAttribute(fused_kernel, cudaFuncAttributeMaxDynamicSharedMemorySize, (int)SMEM_BYTES);
  }
  Params p;
  p.x = (const __nv_bfloat16*)d_in[0];
  p.k = (const __nv_bfloat16*)d_in[1];
  p.v = (const __nv_bfloat16*)d_in[2];
  p.shift_k = (const __nv_bfloat16*)d_in[3];
  p.ssm_k = (const __nv_bfloat16*)d_in[4];
  p.ssm_D = (const __nv_bfloat16*)d_in[5];
  p.wg = (const __nv_bfloat16*)d_in[7];
  p.wu = (const __nv_bfloat16*)d_in[8];
  p.wd = (const __nv_bfloat16*)d_in[9];
  make_map(enc, &p.m_x, p.x, D_, S_, D_, 32, 128, CU_TENSOR_MAP_SWIZZLE_64B);
  make_map(enc, &p.m_wg64, p.wg, F_, D_, F_, 64, 32, CU_TENSOR_MAP_SWIZZLE_128B);
  make_map(enc, &p.m_wg48, p.wg, F_, D_, F_, 48, 32, CU_TENSOR_MAP_SWIZZLE_128B);
  make_map(enc, &p.m_wu64, p.wu, F_, D_, F_, 64, 32, CU_TENSOR_MAP_SWIZZLE_128B);
  make_map(enc, &p.m_wu48, p.wu, F_, D_, F_, 48, 32, CU_TENSOR_MAP_SWIZZLE_128B);
  make_map(enc, &p.m_h64, ph, F_, S_, HP, 64, 64, CU_TENSOR_MAP_SWIZZLE_128B);
  make_map(enc, &p.m_h48, ph, F_, S_, HP, 48, 64, CU_TENSOR_MAP_SWIZZLE_128B);
  make_map(enc, &p.m_wd, p.wd, D_, F_, D_, 64, 64, CU_TENSOR_MAP_SWIZZLE_128B);
  make_map(enc, &p.m_yT, pyT, S_, D_, S_, 64, 64, CU_TENSOR_MAP_SWIZZLE_128B);
  make_map(enc, &p.m_k, p.k, D_, S_, D_, 64, 131, CU_TENSOR_MAP_SWIZZLE_NONE);
  make_map(enc, &p.m_v, p.v, D_, S_, D_, 64, 128, CU_TENSOR_MAP_SWIZZLE_NONE);
  make_map(enc, &p.m_ur, pur, S_, D_, URP, 64, 64, CU_TENSOR_MAP_SWIZZLE_128B);
  make_map(enc, &p.m_xt, p.x, D_, S_, D_, 64, 64, CU_TENSOR_MAP_SWIZZLE_128B);
  make_map(enc, &p.m_wgp, p.wg, F_, D_, F_, 88, 128, CU_TENSOR_MAP_SWIZZLE_NONE);
  make_map(enc, &p.m_wup, p.wu, F_, D_, F_, 88, 128, CU_TENSOR_MAP_SWIZZLE_NONE);
  make_map(enc, &p.m_out, d_out, D_, S_, D_, 64, 64, CU_TENSOR_MAP_SWIZZLE_128B);
  fused_kernel<<<128, 384, SMEM_BYTES, cudaStreamPerThread>>>(p);
}
```
